```python
import torch

def _softmax(x, axis=-1):
    return torch.softmax(x, dim=axis)
def _gelu(x):
    return torch.nn.functional.gelu(x, approximate="tanh")
def _silu(x):
    return torch.nn.functional.silu(x)
def _sigmoid(x):
    return torch.sigmoid(x)
def _layernorm(x, axis=-1, eps=1e-5):
    m = x.mean(dim=axis, keepdim=True)
    v = x.var(dim=axis, keepdim=True, unbiased=False)
    return (x - m) / torch.sqrt(v + eps)
def _scatter_add(tgt, idx, src, axis=0):
    return tgt.clone().index_add_(axis, idx, src)
def _segment_sum(src, seg, n):
    out = torch.zeros((n,) + src.shape[1:], dtype=src.dtype)
    return out.index_add_(0, seg, src)
def _pad(x, pw):
    flat = tuple(v for pair in reversed(pw) for v in pair)
    return torch.nn.functional.pad(x, flat)

kernel_name = 'sequential_preLN__mha_block__dense_activation_relu__prompt'

def setup_inputs():

    _w = (lambda a: (lambda t: t.to(torch.bfloat16) if t.is_floating_point() else t)(torch.as_tensor(a)))
    def _A_setup():
        B, S, D, H = 1, 2048, 576, 32
        return {
            "x": _w((lambda *s: torch.randn(*s, dtype=torch.bfloat16) * 0.05)(B, S, D)),
            "wqkv": _w((lambda *s: torch.randn(*s, dtype=torch.bfloat16) * 0.05)(D, 3 * D)),
            "wo": _w((lambda *s: torch.randn(*s, dtype=torch.bfloat16) * 0.05)(D, D)),
        }
    _A_in = _A_setup()

    def _B_setup():
        B, S, D, Dff = 1, 2048, 576, 4608
        return {
            "x": _w((lambda *s: torch.randn(*s, dtype=torch.bfloat16) * 0.05)(B, S, D)),
            "w1": _w((lambda *s: torch.randn(*s, dtype=torch.bfloat16) * 0.05)(D, Dff)),
            "w2": _w((lambda *s: torch.randn(*s, dtype=torch.bfloat16) * 0.05)(Dff, D)),
        }
    _B_in = _B_setup()

    return {
        "A_x": _A_in["x"],
        "A_wqkv": _A_in["wqkv"],
        "A_wo": _A_in["wo"],
        "B_x": _B_in["x"],
        "B_w1": _B_in["w1"],
        "B_w2": _B_in["w2"],
    }

def reference(A_x, A_wqkv, A_wo, B_x, B_w1, B_w2):
    def _A_ref(x, wqkv, wo):
        B, S, D = x.shape
        H = 32
        Dh = D // H
        qkv = (lambda x, *d: x.permute(*d))((x @ wqkv).reshape(B, S, 3, H, Dh), 2, 0, 3, 1, 4)
        q, k, v = qkv[0], qkv[1], qkv[2]
        scores = torch.einsum("bhqd,bhkd->bhqk", q, k) * (Dh ** -0.5)
        p = _softmax(scores, axis=-1)
        o = torch.einsum("bhqk,bhkd->bhqd", p, v)
        return (lambda x, *d: x.permute(*d))(o, 0, 2, 1, 3).reshape(B, S, D) @ wo

    def _B_ref(x, w1, w2):
        h = torch.einsum("bsd,df->bsf", x, w1)
        zero = torch.zeros_like(h)
        h = torch.maximum(h, zero)
        return torch.einsum("bsf,fd->bsd", h, w2)

    x = A_x
    h = x + _A_ref(_layernorm(x, axis=-1), A_wqkv, A_wo)
    h2 = h + _B_ref(_layernorm(h, axis=-1), B_w1, B_w2)
    return h2
```

```cpp
#include <cuda_runtime.h>
#include <cuda_bf16.h>
#include <cuda.h>
#include <stdint.h>

typedef __nv_bfloat16 bf16;

constexpr int SEQ = 2048, DM = 576, NQKV = 1728, DFF = 4608;
constexpr float LN_EPS = 1e-5f;
constexpr float QSCALE = 0.23570226039551584f * 1.4426950408889634f;

__device__ __align__(1024) bf16 g_main[96 * 2 * SEQ * 8];
__device__ __align__(1024) bf16 g_left[32 * SEQ * 8];
__device__ __align__(1024) bf16 g_OT[DM * SEQ];
__device__ __align__(1024) bf16 g_hc[SEQ * DM];
__device__ __align__(1024) float4 g_acc[16 * 9 * 2 * 2 * 4 * 128];
__device__ __align__(16) float g_nrm[96 * 64];
__device__ __align__(16) float2 g_stat[SEQ];
__device__ __align__(16) float g_cpart[16 * NQKV];
__device__ uint32_t g_wbar[DM];
__device__ float g_hmean[SEQ];
__device__ float4 g_ssq[SEQ];
struct __align__(128) Flag { unsigned int v; };
__device__ Flag g_flag2[16 + 1];
__device__ Flag g_flag4[16 * 9 * 2];

__device__ __forceinline__ uint32_t s2u(const void* p) { return (uint32_t)__cvta_generic_to_shared(p); }
__device__ __forceinline__ void wg_fence() { asm volatile("wgmma.fence.sync.aligned;" ::: "memory"); }
__device__ __forceinline__ void wg_commit() { asm volatile("wgmma.commit_group.sync.aligned;" ::: "memory"); }
template <int N> __device__ __forceinline__ void wg_wait() { asm volatile("wgmma.wait_group.sync.aligned %0;" ::"n"(N) : "memory"); }
__device__ __forceinline__ uint64_t mkdesc(uint32_t addr, uint32_t lbo, uint32_t sbo, uint32_t swz) {
  return (uint64_t)((addr & 0x3FFFF) >> 4) | ((uint64_t)(lbo >> 4) << 16) | ((uint64_t)(sbo >> 4) << 32) | ((uint64_t)swz << 62);
}
template <int N> __device__ __forceinline__ void fence_regs(float (&a)[N]) {
#pragma unroll
  for (int i = 0; i < N; i++) asm volatile("" : "+f"(a[i])::"memory");
}
template <int N> __device__ __forceinline__ void fence_regs(uint32_t (&a)[N]) {
#pragma unroll
  for (int i = 0; i < N; i++) asm volatile("" : "+r"(a[i])::"memory");
}
__device__ __forceinline__ void mbar_init(uint32_t b, int c) { asm volatile("mbarrier.init.shared::cta.b64 [%0], %1;" ::"r"(b), "r"(c) : "memory"); }
__device__ __forceinline__ void mbar_init_fence() { asm volatile("fence.mbarrier_init.release.cluster;" ::: "memory"); }
__device__ __forceinline__ void mbar_expect(uint32_t b, int bytes) {
  asm volatile("mbarrier.arrive.expect_tx.shared::cta.b64 _, [%0], %1;" ::"r"(b), "r"(bytes) : "memory");
}
__device__ __forceinline__ void mbar_arrive(uint32_t b) { asm volatile("mbarrier.arrive.shared::cta.b64 _, [%0];" ::"r"(b) : "memory"); }
__device__ __forceinline__ void mbar_arrive_remote(uint32_t b) { asm volatile("mbarrier.arrive.shared::cluster.b64 _, [%0];" ::"r"(b) : "memory"); }
__device__ __forceinline__ void mbar_wait(uint32_t b, uint32_t ph) {
  asm volatile(
      "{\n.reg .pred p;\n.reg .u32 c;\n"
      "mbarrier.try_wait.parity.shared::cta.b64 p, [%0], %1;\n@p bra DONE;\nmov.u32 c, 0;\n"
      "LOOP:\nmbarrier.try_wait.parity.shared::cta.b64 p, [%0], %1;\n@p bra DONE;\n"
      "add.u32 c, c, 1;\nsetp.lt.u32 p, c, 0x200000;\n@p bra LOOP;\ntrap;\nDONE:\n}" ::"r"(b), "r"(ph) : "memory");
}
__device__ __forceinline__ void mbar_wait_cluster(uint32_t b, uint32_t ph) {
  asm volatile(
      "{\n.reg .pred p;\n.reg .u32 c;\n"
      "mbarrier.try_wait.parity.relaxed.cluster.shared::cta.b64 p, [%0], %1;\n@p bra DONE;\nmov.u32 c, 0;\n"
      "LOOP:\nmbarrier.try_wait.parity.relaxed.cluster.shared::cta.b64 p, [%0], %1;\n@p bra DONE;\n"
      "add.u32 c, c, 1;\nsetp.lt.u32 p, c, 0x200000;\n@p bra LOOP;\ntrap;\n"
      "DONE:\nfence.acquire.sync_restrict::shared::cluster.cluster;\n}" ::"r"(b), "r"(ph) : "memory");
}
__device__ __forceinline__ void fence_gpu() { asm volatile("fence.release.gpu;" ::: "memory"); }
template <int SLEEP = 32>
__device__ __forceinline__ void flag_wait(const Flag* f, unsigned int target) {
  unsigned int v;
#pragma unroll 1
  for (int i = 0; i < (1 << 22); i++) {
    asm volatile("ld.acquire.gpu.global.u32 %0, [%1];" : "=r"(v) : "l"(f) : "memory");
    if (v >= target) return;
    if (SLEEP) __nanosleep(SLEEP);
  }
  __trap();
}
__device__ __forceinline__ void flag_add(Flag* f) { asm volatile("red.relaxed.gpu.global.add.u32 [%0], 1;" ::"l"(f) : "memory"); }
__device__ __forceinline__ uint4 ld_volatile(const uint4* p) {
  uint4 v;
  asm volatile("ld.volatile.global.v4.u32 {%0,%1,%2,%3}, [%4];" : "=r"(v.x), "=r"(v.y), "=r"(v.z), "=r"(v.w) : "l"(p) : "memory");
  return v;
}
__device__ __forceinline__ uint32_t mapa(uint32_t a, uint32_t rank) {
  uint32_t r;
  asm("mapa.shared::cluster.u32 %0, %1, %2;" : "=r"(r) : "r"(a), "r"(rank));
  return r;
}
__device__ __forceinline__ uint32_t cluster_rank() { uint32_t r; asm("mov.u32 %0, %%cluster_ctarank;" : "=r"(r)); return r; }
__device__ __forceinline__ void cluster_arrive_relaxed() { asm volatile("barrier.cluster.arrive.relaxed.aligned;" ::: "memory"); }
__device__ __forceinline__ void cluster_wait() { asm volatile("barrier.cluster.wait.aligned;" ::: "memory"); }
__device__ __forceinline__ void named_sync(int id, int n) { asm volatile("bar.sync %0, %1;" ::"r"(id), "r"(n) : "memory"); }
__device__ __forceinline__ void named_arrive(int id, int n) { asm volatile("bar.arrive %0, %1;" ::"r"(id), "r"(n) : "memory"); }
__device__ __forceinline__ void pdl_wait() { asm volatile("griddepcontrol.wait;" ::: "memory"); }
__device__ __forceinline__ void pdl_launch() { asm volatile("griddepcontrol.launch_dependents;" ::: "memory"); }
__device__ __forceinline__ void fence_async_smem() { asm volatile("fence.proxy.async.shared::cta;" ::: "memory"); }
__device__ __forceinline__ void tma2d(uint32_t dst, const CUtensorMap* tm, int c0, int c1, uint32_t bar) {
  asm volatile("cp.async.bulk.tensor.2d.shared::cluster.global.mbarrier::complete_tx::bytes [%0], [%1, {%3, %4}], [%2];"
               ::"r"(dst), "l"(tm), "r"(bar), "r"(c0), "r"(c1) : "memory");
}
__device__ __forceinline__ void tma2d_mc(uint32_t dst, const CUtensorMap* tm, int c0, int c1, uint32_t bar) {
  asm volatile("cp.async.bulk.tensor.2d.shared::cluster.global.mbarrier::complete_tx::bytes.multicast::cluster [%0], [%1, {%3, %4}], [%2], %5;"
               ::"r"(dst), "l"(tm), "r"(bar), "r"(c0), "r"(c1), "h"((uint16_t)3) : "memory");
}
__device__ __forceinline__ void tma3d(uint32_t dst, const CUtensorMap* tm, int c0, int c1, int c2, uint32_t bar) {
  asm volatile("cp.async.bulk.tensor.3d.shared::cluster.global.mbarrier::complete_tx::bytes [%0], [%1, {%3, %4, %5}], [%2];"
               ::"r"(dst), "l"(tm), "r"(bar), "r"(c0), "r"(c1), "r"(c2) : "memory");
}
__device__ __forceinline__ void bulk_load(uint32_t dst, const void* src, int bytes, uint32_t bar) {
  asm volatile("cp.async.bulk.shared::cluster.global.mbarrier::complete_tx::bytes [%0], [%1], %2, [%3];"
               ::"r"(dst), "l"(src), "r"(bytes), "r"(bar) : "memory");
}
__device__ __forceinline__ void bulk_store(void* dst, uint32_t src, int bytes) {
  asm volatile("cp.async.bulk.global.shared::cta.bulk_group [%0], [%1], %2;" ::"l"(dst), "r"(src), "r"(bytes) : "memory");
}
__device__ __forceinline__ void prefetch_tm(const CUtensorMap* tm) { asm volatile("prefetch.tensormap [%0];" ::"l"(tm) : "memory"); }
__device__ __forceinline__ uint32_t pack_bf16(float lo, float hi) {
  uint32_t r; asm("cvt.rn.bf16x2.f32 %0, %1, %2;" : "=r"(r) : "f"(hi), "f"(lo)); return r;
}
__device__ __forceinline__ float bf_lo(uint32_t v) { return __uint_as_float(v << 16); }
__device__ __forceinline__ float bf_hi(uint32_t v) { return __uint_as_float(v & 0xffff0000u); }
__device__ __forceinline__ float ex2(float x) { float y; asm("ex2.approx.ftz.f32 %0, %1;" : "=f"(y) : "f"(x)); return y; }
__device__ __forceinline__ float rcp(float x) { float y; asm("rcp.approx.ftz.f32 %0, %1;" : "=f"(y) : "f"(x)); return y; }
__device__ __forceinline__ void sts32(uint32_t a, uint32_t v) { asm volatile("st.shared.u32 [%0], %1;" ::"r"(a), "r"(v) : "memory"); }
__device__ __forceinline__ void sts128(uint32_t a, uint4 v) {
  asm volatile("st.shared.v4.u32 [%0], {%1,%2,%3,%4};" ::"r"(a), "r"(v.x), "r"(v.y), "r"(v.z), "r"(v.w) : "memory");
}
__device__ __forceinline__ uint4 lds128(uint32_t a) {
  uint4 v; asm volatile("ld.shared.v4.u32 {%0,%1,%2,%3}, [%4];" : "=r"(v.x), "=r"(v.y), "=r"(v.z), "=r"(v.w) : "r"(a) : "memory"); return v;
}
__device__ __forceinline__ float4 lds128f(uint32_t a) {
  float4 v; asm volatile("ld.shared.v4.f32 {%0,%1,%2,%3}, [%4];" : "=f"(v.x), "=f"(v.y), "=f"(v.z), "=f"(v.w) : "r"(a) : "memory"); return v;
}
__device__ __forceinline__ float2 lds64f(uint32_t a) {
  float2 v; asm volatile("ld.shared.v2.f32 {%0,%1}, [%2];" : "=f"(v.x), "=f"(v.y) : "r"(a) : "memory"); return v;
}
__device__ __forceinline__ void stsm_x4(uint32_t a, uint32_t r0, uint32_t r1, uint32_t r2, uint32_t r3) {
  asm volatile("stmatrix.sync.aligned.m8n8.x4.shared.b16 [%0], {%1,%2,%3,%4};" ::"r"(a), "r"(r0), "r"(r1), "r"(r2), "r"(r3) : "memory");
}
__device__ __forceinline__ void stsm_x4_t(uint32_t a, uint32_t r0, uint32_t r1, uint32_t r2, uint32_t r3) {
  asm volatile("stmatrix.sync.aligned.m8n8.x4.trans.shared.b16 [%0], {%1,%2,%3,%4};" ::"r"(a), "r"(r0), "r"(r1), "r"(r2), "r"(r3) : "memory");
}
__device__ __forceinline__ void stsm_x2_t(uint32_t a, uint32_t r0, uint32_t r1) {
  asm volatile("stmatrix.sync.aligned.m8n8.x2.trans.shared.b16 [%0], {%1,%2};" ::"r"(a), "r"(r0), "r"(r1) : "memory");
}
__device__ __forceinline__ float warp_sum(float v) {
#pragma unroll
  for (int o = 16; o; o >>= 1) v += __shfl_xor_sync(~0u, v, o);
  return v;
}

__device__ __forceinline__ void wgmma_ss_n240_01(float (&d)[120], uint64_t da, uint64_t db, int sd) {
  asm volatile("{\n.reg .pred p;\nsetp.ne.b32 p, %122, 0;\n"
    "wgmma.mma_async.sync.aligned.m64n240k16.f32.bf16.bf16 {%0,%1,%2,%3,%4,%5,%6,%7,%8,%9,%10,%11,%12,%13,%14,%15,%16,%17,%18,%19,%20,"
    "%21,%22,%23,%24,%25,%26,%27,%28,%29,%30,%31,%32,%33,%34,%35,%36,%37,%38,%39,%40,%41,%42,%43,%44,%45,%46,%47,%48,%49,%50,%51,%52,"
    "%53,%54,%55,%56,%57,%58,%59,%60,%61,%62,%63,%64,%65,%66,%67,%68,%69,%70,%71,%72,%73,%74,%75,%76,%77,%78,%79,%80,%81,%82,%83,%84,"
    "%85,%86,%87,%88,%89,%90,%91,%92,%93,%94,%95,%96,%97,%98,%99,%100,%101,%102,%103,%104,%105,%106,%107,%108,%109,%110,%111,%112,%113,"
    "%114,%115,%116,%117,%118,%119}, %120, %121, p, 1, 1, 0, 1;\n}\n"
    : "+f"(d[0]), "+f"(d[1]), "+f"(d[2]), "+f"(d[3]), "+f"(d[4]), "+f"(d[5]), "+f"(d[6]), "+f"(d[7]), "+f"(d[8]), "+f"(d[9]), "+f"(d[10]),
    "+f"(d[11]), "+f"(d[12]), "+f"(d[13]), "+f"(d[14]), "+f"(d[15]), "+f"(d[16]), "+f"(d[17]), "+f"(d[18]), "+f"(d[19]), "+f"(d[20]), "+f"(d[21]),
    "+f"(d[22]), "+f"(d[23]), "+f"(d[24]), "+f"(d[25]), "+f"(d[26]), "+f"(d[27]), "+f"(d[28]), "+f"(d[29]), "+f"(d[30]), "+f"(d[31]), "+f"(d[32]),
    "+f"(d[33]), "+f"(d[34]), "+f"(d[35]), "+f"(d[36]), "+f"(d[37]), "+f"(d[38]), "+f"(d[39]), "+f"(d[40]), "+f"(d[41]), "+f"(d[42]), "+f"(d[43]),
    "+f"(d[44]), "+f"(d[45]), "+f"(d[46]), "+f"(d[47]), "+f"(d[48]), "+f"(d[49]), "+f"(d[50]), "+f"(d[51]), "+f"(d[52]), "+f"(d[53]), "+f"(d[54]),
    "+f"(d[55]), "+f"(d[56]), "+f"(d[57]), "+f"(d[58]), "+f"(d[59]), "+f"(d[60]), "+f"(d[61]), "+f"(d[62]), "+f"(d[63]), "+f"(d[64]), "+f"(d[65]),
    "+f"(d[66]), "+f"(d[67]), "+f"(d[68]), "+f"(d[69]), "+f"(d[70]), "+f"(d[71]), "+f"(d[72]), "+f"(d[73]), "+f"(d[74]), "+f"(d[75]), "+f"(d[76]),
    "+f"(d[77]), "+f"(d[78]), "+f"(d[79]), "+f"(d[80]), "+f"(d[81]), "+f"(d[82]), "+f"(d[83]), "+f"(d[84]), "+f"(d[85]), "+f"(d[86]), "+f"(d[87]),
    "+f"(d[88]), "+f"(d[89]), "+f"(d[90]), "+f"(d[91]), "+f"(d[92]), "+f"(d[93]), "+f"(d[94]), "+f"(d[95]), "+f"(d[96]), "+f"(d[97]), "+f"(d[98]),
    "+f"(d[99]), "+f"(d[100]), "+f"(d[101]), "+f"(d[102]), "+f"(d[103]), "+f"(d[104]), "+f"(d[105]), "+f"(d[106]), "+f"(d[107]), "+f"(d[108]),
    "+f"(d[109]), "+f"(d[110]), "+f"(d[111]), "+f"(d[112]), "+f"(d[113]), "+f"(d[114]), "+f"(d[115]), "+f"(d[116]), "+f"(d[117]), "+f"(d[118]),
    "+f"(d[119])
    : "l"(da), "l"(db), "r"(sd));
}
__device__ __forceinline__ void wgmma_rs_n64_00(float (&d)[32], uint32_t a0, uint32_t a1, uint32_t a2, uint32_t a3, uint64_t db, int sd) {
  asm volatile("{\n.reg .pred p;\nsetp.ne.b32 p, %37, 0;\n"
    "wgmma.mma_async.sync.aligned.m64n64k16.f32.bf16.bf16 {%0,%1,%2,%3,%4,%5,%6,%7,%8,%9,%10,%11,%12,%13,%14,%15,%16,%17,%18,%19,%20,"
    "%21,%22,%23,%24,%25,%26,%27,%28,%29,%30,%31}, {%32,%33,%34,%35}, %36, p, 1, 1, 0;\n}\n"
    : "+f"(d[0]), "+f"(d[1]), "+f"(d[2]), "+f"(d[3]), "+f"(d[4]), "+f"(d[5]), "+f"(d[6]), "+f"(d[7]), "+f"(d[8]), "+f"(d[9]), "+f"(d[10]),
    "+f"(d[11]), "+f"(d[12]), "+f"(d[13]), "+f"(d[14]), "+f"(d[15]), "+f"(d[16]), "+f"(d[17]), "+f"(d[18]), "+f"(d[19]), "+f"(d[20]), "+f"(d[21]),
    "+f"(d[22]), "+f"(d[23]), "+f"(d[24]), "+f"(d[25]), "+f"(d[26]), "+f"(d[27]), "+f"(d[28]), "+f"(d[29]), "+f"(d[30]), "+f"(d[31])
    : "r"(a0), "r"(a1), "r"(a2), "r"(a3), "l"(db), "r"(sd));
}
__device__ __forceinline__ void wgmma_rs_n24_01(float (&d)[12], uint32_t a0, uint32_t a1, uint32_t a2, uint32_t a3, uint64_t db, int sd) {
  asm volatile("{\n.reg .pred p;\nsetp.ne.b32 p, %17, 0;\n"
    "wgmma.mma_async.sync.aligned.m64n24k16.f32.bf16.bf16 {%0,%1,%2,%3,%4,%5,%6,%7,%8,%9,%10,%11}, {%12,%13,%14,%15}, %16, p, 1, 1,"
    " 1;\n}\n"
    : "+f"(d[0]), "+f"(d[1]), "+f"(d[2]), "+f"(d[3]), "+f"(d[4]), "+f"(d[5]), "+f"(d[6]), "+f"(d[7]), "+f"(d[8]), "+f"(d[9]), "+f"(d[10]),
    "+f"(d[11])
    : "r"(a0), "r"(a1), "r"(a2), "r"(a3), "l"(db), "r"(sd));
}
__device__ __forceinline__ void wgmma_ss_n152_11(float (&d)[76], uint64_t da, uint64_t db, int sd) {
  asm volatile("{\n.reg .pred p;\nsetp.ne.b32 p, %78, 0;\n"
    "wgmma.mma_async.sync.aligned.m64n152k16.f32.bf16.bf16 {%0,%1,%2,%3,%4,%5,%6,%7,%8,%9,%10,%11,%12,%13,%14,%15,%16,%17,%18,%19,%20,"
    "%21,%22,%23,%24,%25,%26,%27,%28,%29,%30,%31,%32,%33,%34,%35,%36,%37,%38,%39,%40,%41,%42,%43,%44,%45,%46,%47,%48,%49,%50,%51,%52,"
    "%53,%54,%55,%56,%57,%58,%59,%60,%61,%62,%63,%64,%65,%66,%67,%68,%69,%70,%71,%72,%73,%74,%75}, %76, %77, p, 1, 1, 1, 1;\n}\n"
    : "+f"(d[0]), "+f"(d[1]), "+f"(d[2]), "+f"(d[3]), "+f"(d[4]), "+f"(d[5]), "+f"(d[6]), "+f"(d[7]), "+f"(d[8]), "+f"(d[9]), "+f"(d[10]),
    "+f"(d[11]), "+f"(d[12]), "+f"(d[13]), "+f"(d[14]), "+f"(d[15]), "+f"(d[16]), "+f"(d[17]), "+f"(d[18]), "+f"(d[19]), "+f"(d[20]), "+f"(d[21]),
    "+f"(d[22]), "+f"(d[23]), "+f"(d[24]), "+f"(d[25]), "+f"(d[26]), "+f"(d[27]), "+f"(d[28]), "+f"(d[29]), "+f"(d[30]), "+f"(d[31]), "+f"(d[32]),
    "+f"(d[33]), "+f"(d[34]), "+f"(d[35]), "+f"(d[36]), "+f"(d[37]), "+f"(d[38]), "+f"(d[39]), "+f"(d[40]), "+f"(d[41]), "+f"(d[42]), "+f"(d[43]),
    "+f"(d[44]), "+f"(d[45]), "+f"(d[46]), "+f"(d[47]), "+f"(d[48]), "+f"(d[49]), "+f"(d[50]), "+f"(d[51]), "+f"(d[52]), "+f"(d[53]), "+f"(d[54]),
    "+f"(d[55]), "+f"(d[56]), "+f"(d[57]), "+f"(d[58]), "+f"(d[59]), "+f"(d[60]), "+f"(d[61]), "+f"(d[62]), "+f"(d[63]), "+f"(d[64]), "+f"(d[65]),
    "+f"(d[66]), "+f"(d[67]), "+f"(d[68]), "+f"(d[69]), "+f"(d[70]), "+f"(d[71]), "+f"(d[72]), "+f"(d[73]), "+f"(d[74]), "+f"(d[75])
    : "l"(da), "l"(db), "r"(sd));
}
__device__ __forceinline__ void wgmma_ss_n192_01(float (&d)[96], uint64_t da, uint64_t db, int sd) {
  asm volatile("{\n.reg .pred p;\nsetp.ne.b32 p, %98, 0;\n"
    "wgmma.mma_async.sync.aligned.m64n192k16.f32.bf16.bf16 {%0,%1,%2,%3,%4,%5,%6,%7,%8,%9,%10,%11,%12,%13,%14,%15,%16,%17,%18,%19,%20,"
    "%21,%22,%23,%24,%25,%26,%27,%28,%29,%30,%31,%32,%33,%34,%35,%36,%37,%38,%39,%40,%41,%42,%43,%44,%45,%46,%47,%48,%49,%50,%51,%52,"
    "%53,%54,%55,%56,%57,%58,%59,%60,%61,%62,%63,%64,%65,%66,%67,%68,%69,%70,%71,%72,%73,%74,%75,%76,%77,%78,%79,%80,%81,%82,%83,%84,"
    "%85,%86,%87,%88,%89,%90,%91,%92,%93,%94,%95}, %96, %97, p, 1, 1, 0, 1;\n}\n"
    : "+f"(d[0]), "+f"(d[1]), "+f"(d[2]), "+f"(d[3]), "+f"(d[4]), "+f"(d[5]), "+f"(d[6]), "+f"(d[7]), "+f"(d[8]), "+f"(d[9]), "+f"(d[10]),
    "+f"(d[11]), "+f"(d[12]), "+f"(d[13]), "+f"(d[14]), "+f"(d[15]), "+f"(d[16]), "+f"(d[17]), "+f"(d[18]), "+f"(d[19]), "+f"(d[20]), "+f"(d[21]),
    "+f"(d[22]), "+f"(d[23]), "+f"(d[24]), "+f"(d[25]), "+f"(d[26]), "+f"(d[27]), "+f"(d[28]), "+f"(d[29]), "+f"(d[30]), "+f"(d[31]), "+f"(d[32]),
    "+f"(d[33]), "+f"(d[34]), "+f"(d[35]), "+f"(d[36]), "+f"(d[37]), "+f"(d[38]), "+f"(d[39]), "+f"(d[40]), "+f"(d[41]), "+f"(d[42]), "+f"(d[43]),
    "+f"(d[44]), "+f"(d[45]), "+f"(d[46]), "+f"(d[47]), "+f"(d[48]), "+f"(d[49]), "+f"(d[50]), "+f"(d[51]), "+f"(d[52]), "+f"(d[53]), "+f"(d[54]),
    "+f"(d[55]), "+f"(d[56]), "+f"(d[57]), "+f"(d[58]), "+f"(d[59]), "+f"(d[60]), "+f"(d[61]), "+f"(d[62]), "+f"(d[63]), "+f"(d[64]), "+f"(d[65]),
    "+f"(d[66]), "+f"(d[67]), "+f"(d[68]), "+f"(d[69]), "+f"(d[70]), "+f"(d[71]), "+f"(d[72]), "+f"(d[73]), "+f"(d[74]), "+f"(d[75]), "+f"(d[76]),
    "+f"(d[77]), "+f"(d[78]), "+f"(d[79]), "+f"(d[80]), "+f"(d[81]), "+f"(d[82]), "+f"(d[83]), "+f"(d[84]), "+f"(d[85]), "+f"(d[86]), "+f"(d[87]),
    "+f"(d[88]), "+f"(d[89]), "+f"(d[90]), "+f"(d[91]), "+f"(d[92]), "+f"(d[93]), "+f"(d[94]), "+f"(d[95])
    : "l"(da), "l"(db), "r"(sd));
}
__device__ __forceinline__ void wgmma_rs_n64_01(float (&d)[32], uint32_t a0, uint32_t a1, uint32_t a2, uint32_t a3, uint64_t db, int sd) {
  asm volatile("{\n.reg .pred p;\nsetp.ne.b32 p, %37, 0;\n"
    "wgmma.mma_async.sync.aligned.m64n64k16.f32.bf16.bf16 {%0,%1,%2,%3,%4,%5,%6,%7,%8,%9,%10,%11,%12,%13,%14,%15,%16,%17,%18,%19,%20,"
    "%21,%22,%23,%24,%25,%26,%27,%28,%29,%30,%31}, {%32,%33,%34,%35}, %36, p, 1, 1, 1;\n}\n"
    : "+f"(d[0]), "+f"(d[1]), "+f"(d[2]), "+f"(d[3]), "+f"(d[4]), "+f"(d[5]), "+f"(d[6]), "+f"(d[7]), "+f"(d[8]), "+f"(d[9]), "+f"(d[10]),
    "+f"(d[11]), "+f"(d[12]), "+f"(d[13]), "+f"(d[14]), "+f"(d[15]), "+f"(d[16]), "+f"(d[17]), "+f"(d[18]), "+f"(d[19]), "+f"(d[20]), "+f"(d[21]),
    "+f"(d[22]), "+f"(d[23]), "+f"(d[24]), "+f"(d[25]), "+f"(d[26]), "+f"(d[27]), "+f"(d[28]), "+f"(d[29]), "+f"(d[30]), "+f"(d[31])
    : "r"(a0), "r"(a1), "r"(a2), "r"(a3), "l"(db), "r"(sd));
}

constexpr int QKV_STAGE = 16384 + 8 * 4096, QKV_NST = 4;
constexpr int QKV_SMEM = QKV_NST * QKV_STAGE + 1024 + 1024 + 2592 + 1024;

__global__ void __launch_bounds__(384) k_qkv(const __grid_constant__ CUtensorMap tmX, const __grid_constant__ CUtensorMap tmW,
                                             const bf16* __restrict__ x, const bf16* __restrict__ w) {
  extern __shared__ uint8_t smem_raw[];
  const uint32_t sb = (s2u(smem_raw) + 1023) & ~1023u;
  const uint32_t s_out = sb + QKV_STAGE;
  const uint32_t s_stat = sb + QKV_NST * QKV_STAGE;
  const uint32_t s_col = s_stat + 1024;
  const uint32_t s_bar = s_col + 896;
  const uint32_t s_tmp = s_bar + 128;
  const int tid = threadIdx.x, warp = __shfl_sync(~0u, tid >> 5, 0), lane = tid & 31;
  const uint32_t rank = cluster_rank();
  const int n = blockIdx.x >> 4, m = blockIdx.x & 15, sh = (4 - n) & 3;
  const int stage_bytes = sh > 1 ? QKV_STAGE : QKV_STAGE - 4096;
  if (tid == 256) {
    prefetch_tm(&tmX); prefetch_tm(&tmW);
    for (int i = 0; i < QKV_NST; i++) { mbar_init(s_bar + 8 * i, 1); mbar_init(s_bar + 32 + 8 * i, 16); }
    mbar_init(s_bar + 64, 8);
    mbar_init_fence();
    mbar_expect(s_bar, stage_bytes);
    tma2d(sb, &tmX, 0, m * 128, s_bar);
  }
  __syncwarp();
  cluster_arrive_relaxed();
  if (warp == 8) {
    cluster_wait();
    if (lane == 0) {
      const int b1 = rank ? (sh > 1 ? 8 : 7) : 4;
#pragma unroll 1
      for (int s = 0; s < 9; s++) {
        const uint32_t st = sb + (s & 3) * QKV_STAGE, fb = s_bar + 8 * (s & 3);
        if (s >= QKV_NST) mbar_wait(s_bar + 32 + 8 * (s & 3), s >> 3);
        if (s) mbar_expect(fb, stage_bytes);
#pragma unroll 1
        for (int b = rank * 4; b < b1; b++) tma2d_mc(st + 16384 + b * 4096, &tmW, n * 216 - 8 * sh + b * 32, s * 64, fb);
        if (s) tma2d(st, &tmX, s * 64, m * 128, fb);
      }
    }
    pdl_launch();
  } else if (warp > 8) {
    const int t = tid - 288, sw = warp - 9;
    cluster_wait();
    mbar_wait(s_bar, 0);
    {
      uint32_t v[6][9];
      uint4 wv[12];
      const uint32_t* xr = (const uint32_t*)(x + (size_t)(m * 128 + n * 16 + sw * 5) * DM) + lane;
      const uint4* wr = (const uint4*)(w + (size_t)(m * 36 + sw * 12) * NQKV + n * 216) + min(lane, 26);
#pragma unroll
      for (int r = 0; r < 12; r++) wv[r] = __ldg(wr + r * (NQKV / 8));
#pragma unroll
      for (int r = 0; r < 6; r++)
#pragma unroll
        for (int i = 0; i < 9; i++) v[r][i] = __ldg(xr + r * 288 + i * 32);
      float c[8] = {0.f, 0.f, 0.f, 0.f, 0.f, 0.f, 0.f, 0.f};
#pragma unroll
      for (int r = 0; r < 12; r++) {
        c[0] += bf_lo(wv[r].x); c[1] += bf_hi(wv[r].x); c[2] += bf_lo(wv[r].y); c[3] += bf_hi(wv[r].y);
        c[4] += bf_lo(wv[r].z); c[5] += bf_hi(wv[r].z); c[6] += bf_lo(wv[r].w); c[7] += bf_hi(wv[r].w);
      }
      if (lane < 27) {
        sts128(s_tmp + sw * 864 + lane * 32, make_uint4(__float_as_uint(c[0]), __float_as_uint(c[1]), __float_as_uint(c[2]), __float_as_uint(c[3])));
        sts128(s_tmp + sw * 864 + lane * 32 + 16, make_uint4(__float_as_uint(c[4]), __float_as_uint(c[5]), __float_as_uint(c[6]), __float_as_uint(c[7])));
      }
      named_sync(5, 96);
      if (t < 54) {
        const float4 a = lds128f(s_tmp + 16 * t), b = lds128f(s_tmp + 864 + 16 * t), d = lds128f(s_tmp + 1728 + 16 * t);
        __stcg((uint4*)(g_cpart + m * NQKV + n * 216) + t, make_uint4(__float_as_uint(a.x + b.x + d.x) | 1, __float_as_uint(a.y + b.y + d.y) | 1,
                                                                     __float_as_uint(a.z + b.z + d.z) | 1, __float_as_uint(a.w + b.w + d.w) | 1));
      }
      float s1[6], s2[6], x0[6];
#pragma unroll
      for (int r = 0; r < 6; r++) {
        x0[r] = bf_lo(__shfl_sync(~0u, v[r][0], 0));
        s1[r] = s2[r] = 0.f;
#pragma unroll
        for (int i = 0; i < 9; i++) {
          const float a = bf_lo(v[r][i]) - x0[r], b = bf_hi(v[r][i]) - x0[r];
          s1[r] += a + b; s2[r] = fmaf(a, a, fmaf(b, b, s2[r]));
        }
      }
#pragma unroll
      for (int o = 16; o; o >>= 1)
#pragma unroll
        for (int r = 0; r < 6; r++) { s1[r] += __shfl_xor_sync(~0u, s1[r], o); s2[r] += __shfl_xor_sync(~0u, s2[r], o); }
      float a1 = s1[0], a2 = s2[0], a0 = x0[0];
#pragma unroll
      for (int r = 1; r < 6; r++)
        if (lane == r) { a1 = s1[r]; a2 = s2[r]; a0 = x0[r]; }
      a1 *= 1.f / DM;
      if (lane < 6)
        __stcg((uint2*)g_stat + m * 128 + n * 16 + sw * 5 + lane,
               make_uint2(__float_as_uint(a0 + a1) | 1, __float_as_uint(rsqrtf(fmaxf(a2 * (1.f / DM) - a1 * a1, 0.f) + LN_EPS)) | 1));
    }
    if (t >= 64) {
      const uint4* src = (const uint4*)(g_stat + m * 128) + 2 * lane;
      uint4 a, b;
      for (int i = 0;; i++) {
        a = ld_volatile(src); b = ld_volatile(src + 1);
        if (a.x & a.y & a.z & a.w & b.x & b.y & b.z & b.w & 1) break;
        if (i > (1 << 22)) __trap();
      }
      sts128(s_stat + 32 * lane, a);
      sts128(s_stat + 32 * lane + 16, b);
    } else if (t < 54) {
      const uint4* src = (const uint4*)(g_cpart + n * 216) + t;
      float4 c;
      for (int i = 0;; i++) {
        uint32_t ok = 1;
        c = make_float4(0.f, 0.f, 0.f, 0.f);
#pragma unroll
        for (int k = 0; k < 16; k++) {
          const uint4 p = ld_volatile(src + k * (NQKV / 4));
          ok &= p.x & p.y & p.z & p.w;
          c.x += __uint_as_float(p.x); c.y += __uint_as_float(p.y); c.z += __uint_as_float(p.z); c.w += __uint_as_float(p.w);
        }
        if (ok) break;
        if (i > (1 << 22)) __trap();
      }
      sts128(s_col + 16 * t, make_uint4(__float_as_uint(c.x), __float_as_uint(c.y), __float_as_uint(c.z), __float_as_uint(c.w)));
    }
    __syncwarp();
    mbar_wait(s_bar + 64, 0);
#pragma unroll 1
    for (int i = t; i < 512; i += 96) sts32(s_out + 49152 + i * 16 + 12, 0x00003f80u);
    fence_async_smem();
    named_arrive(1, 352);
    if (sw < 2) {
#pragma unroll 1
      for (int i = 0; i < 4; i++) {
        named_sync(6 + i, 320);
        const int cnt = i < 2 ? 2 : 4, slot = (i < 2 ? 2 * i : 4 * i - 4) + lane, grp = i - 1 + lane - cnt;
        if (lane < cnt) bulk_store(g_main + ((size_t)((n * 12 + slot) * 2 + sw) * SEQ + m * 128) * 8, s_out + (slot * 2 + sw) * 2048, 2048);
        else if (sw == 0 && grp >= 0 && lane < cnt + (i == 3 ? 2 : 1))
          bulk_store(g_left + ((size_t)(n * 4 + grp) * SEQ + m * 128) * 8, s_out + 49152 + grp * 2048, 2048);
        asm volatile("cp.async.bulk.commit_group;" ::: "memory");
        __syncwarp();
      }
      asm volatile("cp.async.bulk.wait_group.read 0;" ::: "memory");
    }
  } else {
    const int wg = warp >> 2, q4 = lane & 3, r0 = wg * 64 + (warp & 3) * 16 + (lane >> 2);
    uint32_t off[9], left[4];
    const int l0 = sh + 2 + 2 * q4, lj = l0 >= 9 ? l0 - 9 : l0;
#pragma unroll
    for (int j = 0; j < 9; j++) {
      const int g = j < sh ? j - sh + 9 : j - sh, col = 8 * g + 2 * q4, slot = col / 18, d = col - slot * 18;
      off[j] = s_out + r0 * 16 + (slot - (j < sh ? 4 : 0)) * 4096 + (d >> 3) * 2048 + (d & 7) * 2;
    }
#pragma unroll
    for (int i = 0; i < 4; i++) {
      const int slot = min(max(4 * (i - (l0 >= 9)) + q4, 0), 11);
      left[i] = s_out + 49152 + (slot / 3) * 2048 + r0 * 16 + (slot % 3) * 4 - i * 16384;
    }
    fence_regs(off); fence_regs(left);
    cluster_wait();
    float acc[120];
    const uint64_t dA = mkdesc(sb + wg * 8192, 16, 1024, 1), dB = mkdesc(sb + 16384, 4096, 512, 2);
    const uint32_t peer_empty = mapa(s_bar + 32, rank ^ 1);
#pragma unroll
    for (int s = 0; s < 9; s++) {
      const int so = (s & 3) * (QKV_STAGE >> 4);
      mbar_wait(s_bar + 8 * (s & 3), (s >> 2) & 1);
      wg_fence();
#pragma unroll
      for (int k = 0; k < 4; k++) wgmma_ss_n240_01(acc, dA + (so + k * 2), dB + (so + k * 64), s | k);
      wg_commit();
      if (s >= 1 && s <= 5) {
        wg_wait<1>();
        if (lane == 0) { mbar_arrive(s_bar + 32 + 8 * ((s - 1) & 3)); mbar_arrive_remote(peer_empty + 8 * ((s - 1) & 3)); }
      }
      if (s == 7) {
        wg_wait<1>();
        if (lane == 0) mbar_arrive(s_bar + 64);
      }
    }
    wg_wait<0>();
    fence_regs(acc);
    named_sync(1, 352);
    const float2 st0 = lds64f(s_stat + 8 * r0), st1 = lds64f(s_stat + 8 * (r0 + 8));
    const float sa = n <= 2 ? QSCALE : 1.f, sc = n < 2 ? QSCALE : 1.f;
    const float a0[2] = {st0.y * sa, st0.y * sc}, a1[2] = {st1.y * sa, st1.y * sc};
    const uint32_t cb = s_col + 8 * q4 - 32 * sh;
    const int t = tid & 127;
    float2 c[3] = {lds64f(cb), lds64f(cb + 32), lds64f(cb + 64)};
#pragma unroll
    for (int j = 0; j < 30; j++) {
      const float2 cj = c[j % 3];
      if (j < 27) c[j % 3] = lds64f(cb + 32 * (j + 3));
      if ((j >= 3 && j < 27) || (j >= sh && j < sh + 27)) {
        const uint32_t o = (lj == j % 9 ? left[j / 9] : off[j % 9]) + (j / 9) * 16384;
        sts32(o, pack_bf16((acc[4 * j] - st0.x * cj.x) * a0[j >= 20], (acc[4 * j + 1] - st0.x * cj.y) * a0[j >= 20]));
        sts32(o + 128, pack_bf16((acc[4 * j + 2] - st1.x * cj.x) * a1[j >= 20], (acc[4 * j + 3] - st1.x * cj.y) * a1[j >= 20]));
      }
      if (j == 7 || j == 11 || j == 20 || j == 29) {
        fence_async_smem();
        named_arrive(j == 7 ? 6 : (j == 11 ? 7 : (j == 20 ? 8 : 9)), 320);
      }
    }
    named_sync(3 + wg, 128);
#pragma unroll 2
    for (int it = 0; it < 6; it++) {
      const int slot = it * 2 + (t >> 6), row = wg * 64 + (t & 63);
      const uint32_t a = s_out + slot * 4096 + row * 16;
      const uint4 u0 = lds128(a), u1 = lds128(a + 2048);
      uint32_t u2;
      asm volatile("ld.shared.u32 %0, [%1];" : "=r"(u2) : "r"(s_out + 49152 + (slot / 3) * 2048 + row * 16 + (slot % 3) * 4) : "memory");
      const uint32_t e[8] = {u0.x, u0.y, u0.z, u0.w, u1.x, u1.y, u1.z, u1.w};
      __nv_bfloat162 s0 = __hmul2(*(const __nv_bfloat162*)&u2, *(const __nv_bfloat162*)&u2);
      __nv_bfloat162 s1 = __hmul2(*(const __nv_bfloat162*)&e[0], *(const __nv_bfloat162*)&e[0]);
#pragma unroll
      for (int i = 1; i < 8; i += 2) s0 = __hfma2(*(const __nv_bfloat162*)&e[i], *(const __nv_bfloat162*)&e[i], s0);
#pragma unroll
      for (int i = 2; i < 8; i += 2) s1 = __hfma2(*(const __nv_bfloat162*)&e[i], *(const __nv_bfloat162*)&e[i], s1);
      const float nn = (__low2float(s0) + __high2float(s0)) + (__low2float(s1) + __high2float(s1));
      const uint32_t mx = __reduce_max_sync(~0u, __float_as_uint(nn) & 0x7fffffffu);
      if (lane == 0) g_nrm[(n * 12 + slot) * 64 + m * 4 + (row >> 5)] = __uint_as_float(mx);
    }
  }
}

constexpr uint32_t POLY_MASK = 0xB6u;
__device__ __forceinline__ uint32_t exp2_pair(float t0, float t1, uint32_t one, uint32_t cA) {
  uint32_t tp, u, s, D;
  asm("prmt.b32 %0, %1, %2, 0x6521;" : "=r"(tp) : "r"(__float_as_uint(t0)), "r"(__float_as_uint(t1)));
  asm("lop3.b32 %0, %1, 0x007f007f, %2, 0xea;" : "=r"(u) : "r"(tp), "r"(one));
  asm("fma.rn.bf16x2 %0, %1, %2, %3;" : "=r"(s) : "r"(u), "r"(cA), "r"(0xcf5dcf5du));
  asm("fma.rn.bf16x2 %0, %1, %1, %2;" : "=r"(D) : "r"(s), "r"(0x5ff45ff5u));
  return tp + D;
}
template <int J0>
__device__ __forceinline__ void exp_half(const float (&S)[32], uint32_t (&P)[16], uint32_t one, uint32_t cA) {
#pragma unroll
  for (int j = J0; j < J0 + 4; j++) {
#pragma unroll
    for (int r = 0; r < 2; r++) {
      const float x0 = S[4 * j + 2 * r], x1 = S[4 * j + 2 * r + 1];
      P[2 * j + r] = ((POLY_MASK >> j) & 1) ? exp2_pair(x0, x1, one, cA) : pack_bf16(ex2(x0), ex2(x1));
    }
  }
}
constexpr int ATT_KV = 196608;
constexpr int PRJ_ATOM = 36864, PRJ_O = 5 * PRJ_ATOM, PRJ_X = PRJ_O + 3 * 8192, ATT_BAR = ATT_KV + 16 * 1920;
constexpr int ATT_TAB = ATT_BAR + 256, ATT_SMEM = ATT_TAB + 1024 + 1024;
constexpr int A_KV = 0, A_W = 32, A_PATCH = 40, A_STG = 48, A_OFULL = 56, A_OEMPTY = 96, A_X = 136, A_XDONE = 144, A_CNT = 152, A_PASS = 176;

__device__ __forceinline__ void prj_load_w(uint32_t sb, const CUtensorMap* tm, int n, int a0, int na) {
  mbar_expect(sb + ATT_BAR + A_W, na * PRJ_ATOM);
#pragma unroll 1
  for (int i = 3 * a0; i < 3 * (a0 + na); i++) tma2d(sb + i * 12288, tm, n * 144 + (i / 3) * 32, (i % 3) * 192, sb + ATT_BAR + A_W);
}
__device__ __forceinline__ void clear_acc(int tid) {
  float4* z = g_acc + (blockIdx.x - 4) * 2304 + tid;
#pragma unroll
  for (int i = 0; i < 4; i++) z[i * 512] = make_float4(0.f, 0.f, 0.f, 0.f);
  if (tid < 256) z[2048] = make_float4(0.f, 0.f, 0.f, 0.f);
}
__device__ __forceinline__ bool last_of(uint32_t cnt, uint32_t n) {
  uint32_t old;
  asm volatile("atom.acq_rel.cta.shared.add.u32 %0, [%1], 1;" : "=r"(old) : "r"(cnt) : "memory");
  return old == n - 1;
}

__global__ void __launch_bounds__(512) k_attn(const __grid_constant__ CUtensorMap tmOT, const __grid_constant__ CUtensorMap tmWo,
                                              const __grid_constant__ CUtensorMap tmXt, const bf16* __restrict__ wo,
                                              const bf16* __restrict__ w1, const bf16* __restrict__ w2, uint32_t zero) {
  extern __shared__ uint8_t smem_raw[];
  const int tid = threadIdx.x, warp = __shfl_sync(~0u, tid >> 5, 0), lane = tid & 31;
  if (blockIdx.x < 4) {
    const int wr = (blockIdx.x * 16 + warp) * 9;
    const uint32_t* p = (const uint32_t*)(wo + (size_t)wr * DM) + lane;
#pragma unroll 1
    for (int r = 0; r < 9; r++) {
      float s = 0.f;
#pragma unroll
      for (int i = 0; i < 9; i++) { uint32_t u = __ldg(p + r * 288 + i * 32); s += bf_lo(u) + bf_hi(u); }
      s = warp_sum(s);
      s *= 1.f / DM;
      if (lane == 0) g_wbar[wr + r] = pack_bf16(s, s - bf_lo(pack_bf16(s, 0.f)));
    }
    __syncthreads();
    if (tid == 0) { fence_gpu(); flag_add(&g_flag2[16]); }
    pdl_wait();
    pdl_launch();
    if (blockIdx.x == 0) {
      if (tid < 288) g_flag4[tid].v = 0;
    }
    __nanosleep(3000);
    if (tid < 162) {
      const char* src = (const char*)((blockIdx.x & 1) ? w2 : w1) + (size_t)((blockIdx.x >> 1) * 162 + tid) * 16384;
      asm volatile("cp.async.bulk.prefetch.L2.global [%0], %1;" ::"l"(src), "r"(16384) : "memory");
    }
    return;
  }
  const uint32_t sb = (s2u(smem_raw) + 1023) & ~1023u;
  const uint32_t s_out = sb + ATT_KV, s_bar = sb + ATT_BAR;
  const int head = (blockIdx.x - 4) >> 2, qc = (blockIdx.x - 4) & 3;
  if (tid == 0) {
    for (int i = 0; i < 4; i++) mbar_init(s_bar + A_KV + 8 * i, 1);
    mbar_init(s_bar + A_W, 3); mbar_init(s_bar + A_PATCH, 8); mbar_init(s_bar + A_STG, 4);
    for (int i = 0; i < 4; i++) mbar_init(s_bar + A_PASS + 8 * i, 16);
    mbar_init(s_bar + A_X, 1); mbar_init(s_bar + A_XDONE, 4);
    for (int i = 0; i < 5; i++) { mbar_init(s_bar + A_OFULL + 8 * i, 1); mbar_init(s_bar + A_OEMPTY + 8 * i, 4); }
    for (int i = 0; i < 5; i++) sts32(s_bar + A_CNT + 4 * i, 0);
    mbar_init_fence();
    mbar_expect(s_bar, 12288); mbar_expect(s_bar + 8, 36864); mbar_expect(s_bar + 16, 49152); mbar_expect(s_bar + 24, 98304);
    prefetch_tm(&tmOT); prefetch_tm(&tmWo); prefetch_tm(&tmXt);
  }
  if (tid >= 64 && tid < 128) {
    const uint32_t f = ((POLY_MASK >> ((tid >> 3) & 7)) & 1) ? 0x3f80u : 0u;
    sts128(sb + ATT_TAB + (tid - 64) * 16, make_uint4(f * 0x10001u, f, 0, 0));
    fence_async_smem();
  }
  __syncthreads();
  const int wg = warp >> 2, q4 = lane & 3;
  const int tok0 = wg * 128 + (warp & 3) * 16;
  float Oa[2][12], S[32];
  uint32_t P[16], qf[2][8];
#pragma unroll
  for (int i = 0; i < 12; i++) Oa[0][i] = Oa[1][i] = 0.f;
#pragma unroll
  for (int i = 0; i < 32; i++) S[i] = 0.f;
#pragma unroll
  for (int i = 0; i < 16; i++) P[i] = 0;
  const int tokq = qc * 512 + tok0, plane = warp < 6 ? warp : 0, slot = (plane < 3 ? 32 : 64) + head;
  const uint32_t* qp = (const uint32_t*)g_main + ((size_t)head * 2 * SEQ + tokq) * 4 + lane;
  const uint32_t* ql = (const uint32_t*)g_left + ((size_t)(head / 3) * SEQ + tokq + (lane >> 2)) * 4 + head % 3;
  const uint2* np = (const uint2*)(g_nrm + (32 + head) * 64) + lane;
  const uint32_t* nqp = (const uint32_t*)g_nrm + head * 64 + qc * 16 + (lane & 15);
  const char* kv = plane % 3 == 2 ? (const char*)(g_left + (size_t)(slot / 3) * SEQ * 8) : (const char*)(g_main + (size_t)(slot * 2 + plane % 3) * SEQ * 8);
  fence_regs(S); fence_regs(P); fence_regs(Oa[0]); fence_regs(Oa[1]);
  asm volatile("" : "+l"(qp), "+l"(ql), "+l"(np), "+l"(nqp), "+l"(kv)::"memory");
  pdl_wait();
  if (warp < 6 && lane == 0) bulk_load(sb + plane * 8192, kv, 2048, s_bar);
  __syncwarp();
  const bool kpos = q4 == (32 + head) % 3;
#pragma unroll
  for (int b = 0; b < 2; b++) {
    qf[b][0] = __ldcg(qp + b * 256); qf[b][1] = __ldcg(qp + b * 256 + 32);
    qf[b][2] = __ldcg(qp + b * 256 + SEQ * 4); qf[b][3] = __ldcg(qp + b * 256 + SEQ * 4 + 32);
    qf[b][4] = kpos ? __ldcg(ql + b * 256) : 0u; qf[b][5] = kpos ? __ldcg(ql + b * 256 + 32) : 0u;
    const uint32_t mg = q4 == 0 ? 0xbf8043e0u : (q4 == 1 ? 0x00003bb0u : 0u);
    qf[b][6] = mg + zero * (lane + 2 * b + 1); qf[b][7] = mg + zero * (lane + 2 * b + 2);
  }
  bool fast;
  {
    const uint2 nk = np[0], nv = np[1024];
    const uint32_t nq = *nqp;
    const float k2 = __uint_as_float(__reduce_max_sync(~0u, max(nk.x, nk.y)));
    const float v2 = __uint_as_float(__reduce_max_sync(~0u, max(nv.x, nv.y)));
    const float q2 = __uint_as_float(__reduce_max_sync(~0u, nq));
    fast = (q2 * k2 <= 3600.f) && (v2 <= 1.2e24f);
  }
  uint64_t dK0 = mkdesc(sb, 8192, 128, 0), dK1 = mkdesc(sb + 16384, ATT_TAB - 16384, 128, 0), dV = mkdesc(sb + 24576, 128, 8192, 0);
  auto qk = [&](const uint32_t (&q)[8], int off) {
    wgmma_rs_n64_00(S, q[0], q[1], q[2], q[3], dK0 + off, 0);
    wgmma_rs_n64_00(S, q[4], q[5], q[6], q[7], dK1 - (int64_t)off * 65535, 1);
  };
  auto load_rest = [&]() {
    if (warp < 6 && lane == 0) {
      bulk_load(sb + plane * 8192 + 2048, kv + 2048, 6144, s_bar + 8);
#pragma unroll 1
      for (int c = 1; c < 4; c++) bulk_load(sb + c * 49152 + plane * 8192, kv + c * 8192, 8192, s_bar + (c == 1 ? 16 : 24));
    }
    __syncwarp();
  };
  if (fast) {
    const uint32_t one = 0x3f803f80u + zero, cA = 0x4f124f12u + zero;
    fence_regs(S); fence_regs(P); fence_regs(Oa[0]); fence_regs(Oa[1]); fence_regs(qf[0]); fence_regs(qf[1]);
    mbar_wait(s_bar, 0);
    wg_fence();
    qk(qf[0], 0);
    wg_commit();
    load_rest();
#pragma unroll 1
    for (int it = 0; it < 4; it++) {
#pragma unroll
      for (int u = 0; u < 16; u++) {
        const int t = u >> 1, b = u & 1;
        wg_wait<0>();
        fence_regs(S); fence_regs(P);
        exp_half<0>(S, P, one, cA);
        fence_regs(P);
        wg_fence();
        wgmma_rs_n24_01(Oa[b], P[0], P[1], P[2], P[3], dV + (t * 64), 1);
        wgmma_rs_n24_01(Oa[b], P[4], P[5], P[6], P[7], dV + (t * 64 + 16), 1);
        exp_half<4>(S, P, one, cA);
        fence_regs(S); fence_regs(P);
        if (u == 3) {
          mbar_wait(s_bar + 8, 0);
          if (it == 1) clear_acc(tid);
          if (lane == 0) mbar_arrive(s_bar + A_PASS + 8 * it);
        }
        if (u == 11 && it >= 2) {
          if (lane == 0) {
            uint32_t v;
            asm volatile("{\n.reg .pred p;\nmbarrier.test_wait.parity.shared::cta.b64 p, [%1], 0;\nmov.u32 %0, 1;\n"
                         "@p atom.relaxed.cta.shared.exch.b32 %0, [%2], 1;\n}" : "=r"(v) : "r"(s_bar + A_PASS + 8 * it), "r"(s_bar + A_CNT + 4 * it) : "memory");
            if (v == 0) prj_load_w(sb, &tmWo, head & 3, 2 * (it - 2), 2);
          }
          __syncwarp();
        }
        if (u == 15) mbar_wait(s_bar + (it == 0 ? 16 : 24), 0);
        wg_fence();
        wgmma_rs_n24_01(Oa[b], P[8], P[9], P[10], P[11], dV + (t * 64 + 32), 1);
        wgmma_rs_n24_01(Oa[b], P[12], P[13], P[14], P[15], dV + (t * 64 + 48), 1);
        if (u == 15) wg_commit();
        qk(qf[b ^ 1], u == 15 ? 3072 : ((u + 1) >> 1) * 64);
        wg_commit();
      }
      dK0 += 3072; dK1 -= 3072 * 65535; dV += 3072;
    }
    wg_wait<1>();
    fence_regs(Oa[0]); fence_regs(Oa[1]);
  } else {
    float mx[2][2];
#pragma unroll
    for (int b = 0; b < 2; b++) {
      qf[b][6] = zero * (lane + 2 * b + 1); qf[b][7] = zero * (lane + 2 * b + 2);
      mx[b][0] = mx[b][1] = -INFINITY;
    }
    load_rest();
    clear_acc(tid);
    for (int i = 0; i < 4; i++) mbar_wait(s_bar + 8 * i, 0);
#pragma unroll 1
    for (int t = 0; t < 32; t++) {
#pragma unroll
      for (int b = 0; b < 2; b++) {
        fence_regs(S); fence_regs(qf[b]);
        wg_fence();
        qk(qf[b], 0);
        wg_commit();
        wg_wait<0>();
        fence_regs(S);
#pragma unroll
        for (int r = 0; r < 2; r++) {
          float mm = mx[b][r];
#pragma unroll
          for (int j = 0; j < 8; j++) mm = fmaxf(mm, fmaxf(S[4 * j + 2 * r], S[4 * j + 2 * r + 1]));
          mm = fmaxf(mm, __shfl_xor_sync(~0u, mm, 1));
          mm = fmaxf(mm, __shfl_xor_sync(~0u, mm, 2));
          const float al = ex2(mx[b][r] - mm);
          mx[b][r] = mm;
#pragma unroll
          for (int j = 0; j < 3; j++) { Oa[b][4 * j + 2 * r] *= al; Oa[b][4 * j + 2 * r + 1] *= al; }
#pragma unroll
          for (int j = 0; j < 8; j++) P[2 * j + r] = pack_bf16(ex2(S[4 * j + 2 * r] - mm), ex2(S[4 * j + 2 * r + 1] - mm));
        }
        fence_regs(P); fence_regs(Oa[b]);
        wg_fence();
#pragma unroll
        for (int k = 0; k < 4; k++) wgmma_rs_n24_01(Oa[b], P[4 * k], P[4 * k + 1], P[4 * k + 2], P[4 * k + 3], dV + k * 16, 1);
        wg_commit();
        wg_wait<0>();
        fence_regs(Oa[b]);
      }
      const int adv = (t & 7) == 7 ? 3072 - 7 * 64 : 64;
      dK0 += adv; dK1 -= (int64_t)adv * 65535; dV += adv;
    }
  }
  const int n = head & 3, mt = qc * 8 + (head >> 2);
  {
    const uint32_t ws = s_out + wg * 24 * 272;
#pragma unroll
    for (int b = 0; b < 2; b++) {
      const float i0 = rcp(__shfl_sync(~0u, Oa[b][8], lane | 3)), i1 = rcp(__shfl_sync(~0u, Oa[b][10], lane | 3));
      const uint32_t a = ws + ((lane & 7) + ((lane >> 4) << 3)) * 272 + b * 128 + (warp & 3) * 32 + ((lane >> 3) & 1) * 16;
      stsm_x4_t(a, pack_bf16(Oa[b][0] * i0, Oa[b][1] * i0), pack_bf16(Oa[b][2] * i1, Oa[b][3] * i1),
                pack_bf16(Oa[b][4] * i0, Oa[b][5] * i0), pack_bf16(Oa[b][6] * i1, Oa[b][7] * i1));
      stsm_x2_t(a + (lane < 16 ? 16 * 272 : 0), pack_bf16(Oa[b][8] * i0, Oa[b][9] * i0), pack_bf16(Oa[b][10] * i1, Oa[b][11] * i1));
    }
    wg_wait<0>();
    fence_regs(S);
    named_sync(1 + wg, 128);
    const int t = tid & 127;
    bf16* dst = g_OT + (size_t)(head * 18 + (t >> 4)) * SEQ + qc * 512 + wg * 128 + (t & 15) * 8;
    const uint32_t src = ws + (t >> 4) * 272 + (t & 15) * 16;
    *(uint4*)dst = lds128(src);
    *(uint4*)(dst + 8 * SEQ) = lds128(src + 8 * 272);
    if (t < 32) *(uint4*)(dst + 16 * SEQ) = lds128(src + (16 + 2 * ((64 + head) % 3)) * 272);
    named_sync(1 + wg, 128);
    if (t == 96) {
      fence_gpu();
      flag_add(&g_flag2[qc * 4 + wg]);
      mbar_arrive(s_bar + A_STG);
      pdl_launch();
    }
    if (t == 32 && last_of(s_bar + A_CNT + 16, 4)) {
      mbar_expect(s_bar + A_X, 18432);
      tma2d(sb + PRJ_X, &tmXt, n * 144, mt * 64, s_bar + A_X);
      if (!fast) { mbar_arrive(s_bar + A_W); mbar_arrive(s_bar + A_W); }
      prj_load_w(sb, &tmWo, n, fast ? 4 : 0, fast ? 1 : 5);
    }
    __syncwarp();
  }
  if (wg == 1) {
    if (tid == 128) {
      mbar_wait(s_bar + A_STG, 0);
      flag_wait<0>(&g_flag2[qc * 4 + ((mt & 7) >> 1)], 32);
      asm volatile("fence.proxy.async.global;" ::: "memory");
#pragma unroll 1
      for (int kb = 0; kb < 9; kb++) {
        const int sl = kb >= 5 ? kb - 5 : kb;
        if (kb == 3) mbar_wait(s_bar + A_XDONE, 0);
        if (kb >= 5) mbar_wait(s_bar + A_OEMPTY + 8 * sl, 0);
        mbar_expect(s_bar + A_OFULL + 8 * sl, 8192);
        tma2d(sb + PRJ_O + sl * 8192, &tmOT, mt * 64, kb * 64, s_bar + A_OFULL + 8 * sl);
      }
    }
  } else if (wg >= 2) {
    if (lane == 0) flag_wait(&g_flag2[16], 4);
    __syncwarp();
    const int t = tid - 256;
    const uint32_t v0 = __ldcg(g_wbar + t), v1 = __ldcg(g_wbar + t + 256), v2 = t < 64 ? __ldcg(g_wbar + t + 512) : 0u;
    const uint32_t a = sb + 4 * PRJ_ATOM + t * 64 + ((2 ^ ((t >> 1) & 3)) << 4);
    mbar_wait(s_bar + A_W, 0);
    sts128(a, make_uint4(v0, 0, 0, 0));
    sts128(a + 256 * 64, make_uint4(v1, 0, 0, 0));
    if (t < 64) sts128(a + 512 * 64, make_uint4(v2, 0, 0, 0));
    fence_async_smem();
    __syncwarp();
    if (lane == 0) mbar_arrive(s_bar + A_PATCH);
  }
  if (wg == 0 || wg == 3) {
    const bool real = wg == (int)zero;
    const int r0 = mt * 64 + (warp & 3) * 16 + (lane >> 2);
    float xm0, xm1;
    float acc[76];
    {
      const float xa = __ldcg(&g_stat[r0]).x, xb = __ldcg(&g_stat[r0 + 8]).x;
      const uint32_t xs = sb + PRJ_X + ((warp & 3) * 16 + (lane >> 2)) * 288 + q4 * 4;
      if (real) mbar_wait(s_bar + A_X, 0);
#pragma unroll
      for (int j = 0; j < 18; j++) {
        uint32_t u0, u1;
        asm volatile("ld.shared.u32 %0, [%1];" : "=r"(u0) : "r"(xs + j * 16) : "memory");
        asm volatile("ld.shared.u32 %0, [%1];" : "=r"(u1) : "r"(xs + 8 * 288 + j * 16) : "memory");
        acc[4 * j] = bf_lo(u0) - xa; acc[4 * j + 1] = bf_hi(u0) - xa; acc[4 * j + 2] = bf_lo(u1) - xb; acc[4 * j + 3] = bf_hi(u1) - xb;
      }
      acc[72] = acc[73] = acc[74] = acc[75] = 0.f;
      xm0 = xa; xm1 = xb;
    }
    const uint64_t dA = mkdesc(sb + PRJ_O, 8192, 1024, 1), dB = mkdesc(sb, PRJ_ATOM, 512, 2);
    uint32_t go[9];
#pragma unroll
    for (int i = 0; i < 9; i++) {
      const int e = i * 32 + lane, r = e / 18;
      go[i] = (mt * 64 + (warp & 3) * 16 + r) * (DM / 8) + n * 18 + e - r * 18;
    }
    fence_regs(acc); fence_regs(go);
    if (real) {
      __syncwarp();
      if (lane == 0) mbar_arrive(s_bar + A_XDONE);
      mbar_wait(s_bar + A_PATCH, 0);
#pragma unroll
      for (int kb = 0; kb < 9; kb++) {
        const int sl = kb % 5;
        mbar_wait(s_bar + A_OFULL + 8 * sl, kb / 5);
        wg_fence();
#pragma unroll
        for (int k = 0; k < 4; k++) wgmma_ss_n152_11(acc, dA + (sl * 512 + k * 128), dB + (kb * 256 + k * 64), 1);
        wg_commit();
        if (kb >= 1 && kb <= 4) {
          wg_wait<1>();
          if (lane == 0) mbar_arrive(s_bar + A_OEMPTY + 8 * (kb - 1));
        }
      }
      wg_wait<0>();
    }
    fence_regs(acc);
    const float m0 = __shfl_sync(~0u, acc[72] + acc[73], lane & ~3), m1 = __shfl_sync(~0u, acc[74] + acc[75], lane & ~3);
    named_sync(1 + wg, 128);
    float q0 = 0.f, q1 = 0.f;
    const uint32_t so = sb + PRJ_O + ((warp & 3) * 16 + (lane & 15)) * 288 + (lane >> 4) * 16;
#pragma unroll
    for (int jj = 0; jj < 9; jj++) {
      uint32_t pk[4];
#pragma unroll
      for (int e = 0; e < 2; e++) {
        const int j = 2 * jj + e;
        const float a = acc[4 * j] - m0, b = acc[4 * j + 1] - m0, c = acc[4 * j + 2] - m1, d = acc[4 * j + 3] - m1;
        q0 += a * a + b * b; q1 += c * c + d * d;
        pk[2 * e] = pack_bf16(a, b); pk[2 * e + 1] = pack_bf16(c, d);
      }
      if (real) stsm_x4(so + jj * 32, pk[0], pk[1], pk[2], pk[3]);
    }
    __syncwarp();
#pragma unroll
    for (int i = 0; i < 9; i++) {
      const uint4 v = lds128(sb + PRJ_O + (warp & 3) * 4608 + (i * 32 + lane) * 16);
      if (real) ((uint4*)g_hc)[go[i]] = v;
    }
    q0 += __shfl_xor_sync(~0u, q0, 1); q0 += __shfl_xor_sync(~0u, q0, 2);
    q1 += __shfl_xor_sync(~0u, q1, 1); q1 += __shfl_xor_sync(~0u, q1, 2);
    if (q4 == 0 && real) { ((float*)&g_ssq[r0])[n] = q0; ((float*)&g_ssq[r0 + 8])[n] = q1; }
    if (q4 == 1 && n == 0 && real) { g_hmean[r0] = xm0 + m0; g_hmean[r0 + 8] = xm1 + m1; }
  }
}

constexpr int FFN_X = 147456, FFN_STAGE = 12288, FFN_NST = 6;
constexpr int FFN_SMEM = FFN_X + FFN_NST * FFN_STAGE + 1024 + 1024;
constexpr int B_FULL = 0, B_EMPTY = 48, B_XFULL = 96, B_XFREE = 168, B_EXCH = 184, B_RED = 216, B_G1 = 272, B_ACC = 280, B_MEAN = 512;
__device__ __forceinline__ int ffn_block(int p, int s) {
  return s == 0 ? 8 : (s < 4 ? ((2 * (p + s)) & 7) : (s < 7 ? ((2 * (p + s - 3) + 1) & 7) : 2 * p + s - 7));
}
struct FfnCtx {
  uint32_t bar, xbase, wg, rank;
  uint64_t dW;
  uint32_t my_x;
  float r0, r1;
  bool lane0, thr0;
};
template <int PAR>
__device__ __forceinline__ void ffn_send(const FfnCtx& c, const float (&a)[32]) {
  constexpr int O = 16;
  const uint32_t eb = c.bar + B_EXCH + 16 * c.wg + 8 * PAR;
  if (c.thr0) mbar_expect(eb, 4096);
  const uint32_t dst = mapa(c.my_x + 2 * 16384 + PAR * 4096, c.rank ^ 1), bar = mapa(eb, c.rank ^ 1);
#pragma unroll
  for (int j = 0; j < 2; j++)
    asm volatile("st.async.weak.shared::cluster.mbarrier::complete_tx::bytes.v4.b32 [%0], {%1,%2,%3,%4}, [%5];"
                 ::"r"(dst + j * 2048), "r"(pack_bf16(a[O + 8 * j], a[O + 8 * j + 1])), "r"(pack_bf16(a[O + 8 * j + 2], a[O + 8 * j + 3])),
                   "r"(pack_bf16(a[O + 8 * j + 4], a[O + 8 * j + 5])), "r"(pack_bf16(a[O + 8 * j + 6], a[O + 8 * j + 7])), "r"(bar) : "memory");
}
__device__ __forceinline__ uint2 ffn_peer(const FfnCtx& c, int par, int j) {
  uint2 p;
  asm volatile("ld.shared.v2.u32 {%0,%1}, [%2];" : "=r"(p.x), "=r"(p.y) : "r"(c.my_x + 2 * 16384 + par * 4096 + (j >> 1) * 2048 + (j & 1) * 8) : "memory");
  return p;
}
template <int PAR>
__device__ __forceinline__ void ffn_reduce(const FfnCtx& c, const float (&a)[32], float4* g, int j) {
  const uint2 p = ffn_peer(c, PAR, j);
  asm volatile("red.global.add.v4.f32 [%0], {%1,%2,%3,%4};" ::"l"(g + j * 128), "f"(a[4 * j] + bf_lo(p.x)), "f"(a[4 * j + 1] + bf_hi(p.x)),
               "f"(a[4 * j + 2] + bf_lo(p.y)), "f"(a[4 * j + 3] + bf_hi(p.y)) : "memory");
}
__device__ __forceinline__ void ffn_finish(const FfnCtx& c, const float (&a)[16], int own, bf16* out, int col, int row) {
  const uint32_t t = threadIdx.x & 127, lr = (t >> 5) * 16 + ((t & 31) >> 2);
  float m0, m1;
  asm volatile("ld.shared.f32 %0, [%1];" : "=f"(m0) : "r"(c.bar + B_MEAN + (c.wg * 64 + lr) * 4) : "memory");
  asm volatile("ld.shared.f32 %0, [%1];" : "=f"(m1) : "r"(c.bar + B_MEAN + (c.wg * 64 + lr + 8) * 4) : "memory");
  const uint32_t hx = c.xbase + own * 16384 + lr * 128 + (t & 3) * 4, h7 = ((lr & 7) ^ (c.rank * 4)) << 4;
  mbar_wait(c.bar + B_ACC + 16 * own + 8 * c.wg, 0);
  uint32_t pk[8];
#pragma unroll
  for (int j = 0; j < 4; j++) {
    const uint2 p = ffn_peer(c, own ^ 1, j);
    const float4 g = lds128f(c.my_x + (3 + own) * 16384 + j * 2048);
    uint32_t h0, h1;
    asm volatile("ld.shared.u32 %0, [%1];" : "=r"(h0) : "r"(hx + ((j << 4) ^ h7)) : "memory");
    asm volatile("ld.shared.u32 %0, [%1];" : "=r"(h1) : "r"(hx + 1024 + ((j << 4) ^ h7)) : "memory");
    pk[2 * j] = pack_bf16(fmaf(a[4 * j] + bf_lo(p.x) + g.x, c.r0, bf_lo(h0) + m0), fmaf(a[4 * j + 1] + bf_hi(p.x) + g.y, c.r0, bf_hi(h0) + m0));
    pk[2 * j + 1] = pack_bf16(fmaf(a[4 * j + 2] + bf_lo(p.y) + g.z, c.r1, bf_lo(h1) + m1), fmaf(a[4 * j + 3] + bf_hi(p.y) + g.w, c.r1, bf_hi(h1) + m1));
  }
  const uint32_t r = (t >> 5) * 16 + (t & 15), st = c.xbase + 5 * 16384 + own * 4096, sw = (((r >> 1) & 3) ^ ((t >> 4) & 1)) << 4;
  stsm_x4(st + r * 64 + sw, pk[0], pk[1], pk[2], pk[3]);
  stsm_x4(st + r * 64 + (sw ^ 32), pk[4], pk[5], pk[6], pk[7]);
  __syncwarp();
  const uint32_t a2 = st + lr * 64 + (((t & 3) ^ ((lr >> 1) & 3)) << 4);
  uint4* dst = (uint4*)(out + (size_t)(row + lr) * DM + col + c.rank * 32) + (t & 3);
  dst[0] = lds128(a2);
  dst[DM] = lds128(a2 + 512);
}
template <int PAR>
__device__ __forceinline__ void ffn_step(FfnCtx& c, const uint32_t (&H)[144], float (&cur)[32], float (&prev)[32], int s,
                                         int m, int p, uint32_t zero) {
  float4* g = g_acc + (size_t)((m * 9 + ffn_block(p, s - 1)) * 4 + c.rank * 2 + c.wg) * 512 + (threadIdx.x & 127);
#pragma unroll
  for (int st = 0; st < 6; st++) {
    mbar_wait(c.bar + B_FULL + 8 * st, PAR);
    wg_fence();
#pragma unroll
    for (int k = 0; k < 6; k++) {
      const int h = 4 * (st * 6 + k);
      wgmma_rs_n64_01(cur, H[h], H[h + 1], H[h + 2], H[h + 3], c.dW + (st * (FFN_STAGE >> 4) + k * 128), st | k);
    }
    wg_commit();
    wg_wait<1>();
    if (c.lane0 && (st > 0 || PAR == 0 || s > 0)) mbar_arrive(c.bar + B_EMPTY + 8 * ((st + 5) % 6));
    if (st == 0) fence_regs(prev);
    if (PAR == 0 || s > 0) {
      if (st == 0) ffn_send<PAR>(c, prev);
      if (PAR == 0 || s < 8) {
        if (st == 1) mbar_wait_cluster(c.bar + B_EXCH + 16 * c.wg + 8 * PAR, ((s - 1) >> 1) & 1);
        if (st >= 1 && st <= 4) ffn_reduce<PAR>(c, prev, g, st - 1);
        if (st == 4) { __syncwarp(); if (c.lane0) mbar_arrive(c.bar + B_RED + 8 * (s - 1)); }
      }
    }
    if (st == 5) fence_regs(prev);
  }
  c.dW += zero;
}

__global__ void __launch_bounds__(384) k_ffn(const __grid_constant__ CUtensorMap tmHc, const __grid_constant__ CUtensorMap tmW1,
                                             const __grid_constant__ CUtensorMap tmW2, bf16* __restrict__ out, uint32_t zero) {
  extern __shared__ uint8_t smem_raw[];
  const uint32_t sb = (s2u(smem_raw) + 1023) & ~1023u;
  const uint32_t s_w = sb + FFN_X, bar = s_w + FFN_NST * FFN_STAGE;
  const int tid = threadIdx.x, warp = __shfl_sync(~0u, tid >> 5, 0), lane = tid & 31;
  const uint32_t rank = cluster_rank();
  const int p = blockIdx.x >> 5, m = (blockIdx.x >> 1) & 15, f = 2 * p + rank;
  if (tid == 0) { prefetch_tm(&tmHc); prefetch_tm(&tmW1); }
  if (tid == 256) {
#pragma unroll
    for (int o = 0; o < B_ACC + 32; o += 8)
      mbar_init(bar + o, (o >= B_EMPTY && o < B_XFULL) || (o >= B_RED && o <= B_G1) ? 8 : (o >= B_XFREE && o < B_EXCH ? 4 : 1));
    mbar_init_fence();
  }
  __syncwarp();
  cluster_arrive_relaxed();
  cluster_wait();

  if (warp >= 8) {
    asm volatile("setmaxnreg.dec.sync.aligned.u32 24;");
    if (tid == 256) {
#pragma unroll 1
      for (int i = 0; i < FFN_NST; i++) {
        if (i == 3) mbar_wait(bar + B_XFULL, 0);
        mbar_expect(bar + B_FULL + 8 * i, FFN_STAGE);
        tma3d(s_w + i * FFN_STAGE, &tmW1, 0, ((i + 4 * p) % 18) * 32, f * 9, bar + B_FULL + 8 * i);
      }
      int slot = 0, ph = 0, kk = (FFN_NST + 4 * p) % 18;
#pragma unroll 1
      for (int i = FFN_NST; i < 54; i++) {
        mbar_wait(bar + B_EMPTY + 8 * slot, ph);
        mbar_expect(bar + B_FULL + 8 * slot, FFN_STAGE);
        tma3d(s_w + slot * FFN_STAGE, &tmW1, 0, kk * 32, f * 9 + (i >= 36 ? 6 : (i >= 18 ? 3 : 0)), bar + B_FULL + 8 * slot);
        if (++kk == 18) kk = 0;
        if (++slot == FFN_NST) { slot = 0; ph ^= 1; }
      }
#pragma unroll 1
      for (int s = 0; s < 9; s++) {
        const int blk = ffn_block(p, s);
#pragma unroll 1
        for (int st = 0; st < 6; st++) {
          mbar_wait(bar + B_EMPTY + 8 * st, ph);
          mbar_expect(bar + B_FULL + 8 * st, FFN_STAGE);
          tma2d(s_w + st * FFN_STAGE, &tmW2, blk * 64, f * 576 + st * 96, bar + B_FULL + 8 * st);
        }
        ph ^= 1;
      }
    } else if (tid == 288) {
      pdl_wait();
#pragma unroll 1
      for (int kb = 0; kb < 9; kb++) {
        if (kb >= 2) mbar_wait(bar + B_XFULL + 8 * (kb - 2), 0);
        mbar_expect(bar + B_XFULL + 8 * kb, 16384);
        tma2d_mc(sb + kb * 16384 + rank * 8192, &tmHc, (kb + 2 * p - (kb + 2 * p >= 9 ? 9 : 0)) * 64, m * 128 + rank * 64, bar + B_XFULL + 8 * kb);
      }
      prefetch_tm(&tmW2);
      if (blockIdx.x < 17) g_flag2[blockIdx.x].v = 0;
#pragma unroll 1
      for (int s = 0; s < 7; s++) {
        mbar_wait(bar + B_RED + 8 * s, 0);
        fence_gpu();
        flag_add(&g_flag4[(m * 9 + ffn_block(p, s)) * 2 + rank]);
      }
    } else if (tid == 320) {
      mbar_wait(bar + B_G1, 0);
#pragma unroll 1
      for (int own = 0; own < 2; own++) {
        const int r = (m * 9 + 2 * p + own) * 2 + rank;
        flag_wait(&g_flag4[r], 3);
        asm volatile("fence.proxy.async.global;" ::: "memory");
#pragma unroll 1
        for (int g = 0; g < 2; g++) {
          mbar_expect(bar + B_ACC + 16 * own + 8 * g, 8192);
          bulk_load(sb + (3 + own) * 16384 + g * 8192, g_acc + (size_t)(r * 2 + g) * 512, 8192, bar + B_ACC + 16 * own + 8 * g);
        }
      }
    } else if (warp == 11) {
      pdl_wait();
      if (lane < 8) ((uint4*)g_stat)[blockIdx.x * 8 + lane] = make_uint4(0, 0, 0, 0);
      ((uint4*)g_cpart)[blockIdx.x * 54 + lane] = make_uint4(0, 0, 0, 0);
      if (lane < 22) ((uint4*)g_cpart)[blockIdx.x * 54 + 32 + lane] = make_uint4(0, 0, 0, 0);
      if (lane == 0) flag_wait(&g_flag4[(m * 9 + 8) * 2 + rank], 4);
      __syncwarp();
#pragma unroll 1
      for (int w = 2 * p; w < 2 * p + 2; w++) {
        const int row = m * 128 + w * 16 + (lane >> 2);
        const float4 qa = __ldcg(&g_ssq[row]);
        const float r0 = rsqrtf(((qa.x + qa.y) + (qa.z + qa.w)) * (1.f / DM) + LN_EPS);
        const float4 qb = __ldcg(&g_ssq[row + 8]);
        const float r1 = rsqrtf(((qb.x + qb.y) + (qb.z + qb.w)) * (1.f / DM) + LN_EPS);
        const float m0 = __ldcg(g_hmean + row), m1 = __ldcg(g_hmean + row + 8);
#pragma unroll 1
        for (int j = 0; j < 4; j++) {
          const int eo = row * (DM / 2) + 256 + rank * 16 + j * 4 + (lane & 3);
          const float4 v = __ldcg(g_acc + (size_t)(((m * 9 + 8) * 2 + rank) * 2 + (w >> 2)) * 512 + j * 128 + (w & 3) * 32 + lane);
          const uint32_t h0 = __ldcg((const uint32_t*)g_hc + eo), h1 = __ldcg((const uint32_t*)g_hc + eo + 8 * 288);
          ((uint32_t*)out)[eo] = pack_bf16(fmaf(v.x, r0, bf_lo(h0) + m0), fmaf(v.y, r0, bf_hi(h0) + m0));
          ((uint32_t*)out)[eo + 8 * 288] = pack_bf16(fmaf(v.z, r1, bf_lo(h1) + m1), fmaf(v.w, r1, bf_hi(h1) + m1));
        }
      }
    }
  } else {
    asm volatile("setmaxnreg.inc.sync.aligned.u32 240;");
    FfnCtx c;
    c.bar = bar; c.rank = rank; c.wg = warp >> 2; c.lane0 = lane == 0; c.thr0 = (tid & 127) == 0;
    c.xbase = sb + c.wg * 8192; c.my_x = c.xbase + (tid & 127) * 16;
    pdl_wait();
    const int r0 = m * 128 + warp * 16 + (lane >> 2);
    const uint4 qa = ld_volatile((const uint4*)&g_ssq[r0]), qb = ld_volatile((const uint4*)&g_ssq[r0 + 8]);
    uint32_t hm;
    asm volatile("ld.volatile.global.u32 %0, [%1];" : "=r"(hm) : "l"(g_hmean + m * 128 + warp * 16 + (lane & 15)) : "memory");
    uint32_t H[144];
    float acc[96];
#pragma unroll
    for (int i = 0; i < 96; i++) acc[i] = 0.f;
    const uint64_t dX = mkdesc(c.xbase, 16, 1024, 1), dW1 = mkdesc(s_w, 4096, 1024, 1);
    uint32_t phase = 0;
#pragma unroll
    for (int ch = 0; ch < 3; ch++) {
      fence_regs(acc);
#pragma unroll 1
      for (int k3 = 0; k3 < 3; k3++) {
#pragma unroll
        for (int i = 0; i < 6; i++) {
          if (ch == 0 && (i & 1) == 0) mbar_wait(bar + B_XFULL + 8 * (k3 * 3 + (i >> 1)), 0);
          mbar_wait(bar + B_FULL + 8 * i, phase);
          const uint64_t d = dW1 + i * (FFN_STAGE >> 4), a = dX + (k3 * 3072 + (i >> 1) * 1024 + (i & 1) * 4);
          wg_fence();
          wgmma_ss_n192_01(acc, a, d, i | k3);
          wgmma_ss_n192_01(acc, a + 2, d + 128, 1);
          wg_commit();
          wg_wait<1>();
          if (lane == 0 && (i | k3)) mbar_arrive(bar + B_EMPTY + 8 * ((i + 5) % 6));
        }
        phase ^= 1;
      }
      wg_wait<0>();
      fence_regs(acc);
      if (lane == 0) mbar_arrive(bar + B_EMPTY + 40);
#pragma unroll
      for (int i = 47; i >= 0; i--)
        asm volatile("cvt.rn.relu.bf16x2.f32 %0, %1, %2;" : "=r"(H[ch * 48 + i]) : "f"(acc[2 * i + 1]), "f"(acc[2 * i]));
      if (ch == 0) {
        sts32(bar + B_MEAN + (warp * 16 + (lane & 15)) * 4, hm);
        c.r0 = rsqrtf(((__uint_as_float(qa.x) + __uint_as_float(qa.y)) + (__uint_as_float(qa.z) + __uint_as_float(qa.w))) * (1.f / DM) + LN_EPS);
        c.r1 = rsqrtf(((__uint_as_float(qb.x) + __uint_as_float(qb.y)) + (__uint_as_float(qb.z) + __uint_as_float(qb.w))) * (1.f / DM) + LN_EPS);
        asm volatile("" : "+f"(c.r0), "+f"(c.r1)::"memory");
        __syncwarp();
      }
    }
    fence_regs(H);
    if (lane == 0) { mbar_arrive(bar + B_G1); mbar_arrive_remote(mapa(bar + B_XFREE + 8 * c.wg, rank ^ 1)); }
    c.dW = mkdesc(s_w, 8192, 1024, 1) | ((uint64_t)(rank * 4) << 49);
    float A0[32], A1[32];
#pragma unroll
    for (int i = 0; i < 32; i++) A0[i] = A1[i] = 0.f;
    fence_regs(A0); fence_regs(A1);
#pragma unroll 1
    for (int s = 0;; s += 2) {
      ffn_step<1>(c, H, A0, A1, s, m, p, zero);
      if (s == 8) break;
      if (s == 0) mbar_wait_cluster(bar + B_XFREE + 8 * c.wg, 0);
      ffn_step<0>(c, H, A1, A0, s + 1, m, p, zero);
    }
    wg_wait<0>();
    fence_regs(A0); fence_regs(A1);
    mbar_wait_cluster(bar + B_EXCH + 16 * c.wg + 8, 1);
    ffn_send<0>(c, A0);
#pragma unroll 1
    for (int own = 0; own < 2; own++) {
      float v[16];
#pragma unroll
      for (int i = 0; i < 16; i++) v[i] = own ? A0[i] : A1[i];
      if (own) mbar_wait_cluster(bar + B_EXCH + 16 * c.wg, 0);
      ffn_finish(c, v, own, out, (2 * p + own) * 64, m * 128 + c.wg * 64);
    }
  }
}

typedef CUresult (*EncodeFn)(CUtensorMap*, CUtensorMapDataType, cuuint32_t, void*, const cuuint64_t*, const cuuint64_t*, const cuuint32_t*,
                             const cuuint32_t*, CUtensorMapInterleave, CUtensorMapSwizzle, CUtensorMapL2promotion, CUtensorMapFloatOOBfill);

static void make_map(EncodeFn enc, CUtensorMap* tm, const void* ptr, int rank, const cuuint64_t* dims, const cuuint64_t* strides,
                     const cuuint32_t* box, CUtensorMapSwizzle sw) {
  const cuuint32_t es[3] = {1, 1, 1};
  enc(tm, CU_TENSOR_MAP_DATA_TYPE_BFLOAT16, rank, (void*)ptr, dims, strides, box, es, CU_TENSOR_MAP_INTERLEAVE_NONE, sw,
      CU_TENSOR_MAP_L2_PROMOTION_L2_128B, CU_TENSOR_MAP_FLOAT_OOB_FILL_NONE);
}
static void make_map2(EncodeFn enc, CUtensorMap* tm, const void* ptr, int cols, int rows, int bc, int br, CUtensorMapSwizzle sw) {
  const cuuint64_t dims[2] = {(cuuint64_t)cols, (cuuint64_t)rows}, strides[1] = {(cuuint64_t)cols * 2};
  const cuuint32_t box[2] = {(cuuint32_t)bc, (cuuint32_t)br};
  make_map(enc, tm, ptr, 2, dims, strides, box, sw);
}
template <typename... KArgs, typename... Args>
static void launch(void (*k)(KArgs...), int grid, int block, int smem, int cluster, bool pdl, Args... args) {
  cudaLaunchConfig_t cfg = {};
  cfg.gridDim = dim3(grid); cfg.blockDim = dim3(block); cfg.dynamicSmemBytes = smem; cfg.stream = cudaStreamPerThread;
  cudaLaunchAttribute at[2];
  int na = 0;
  if (cluster > 1) { at[na].id = cudaLaunchAttributeClusterDimension; at[na].val.clusterDim.x = cluster; at[na].val.clusterDim.y = 1; at[na].val.clusterDim.z = 1; na++; }
  if (pdl) { at[na].id = cudaLaunchAttributeProgrammaticStreamSerialization; at[na].val.programmaticStreamSerializationAllowed = 1; na++; }
  cfg.attrs = at; cfg.numAttrs = na;
  cudaLaunchKernelEx(&cfg, k, args...);
}

extern "C" void kernel_launch(void* const* d_in, const int* in_sizes, int n_in, void* d_out, int out_size) {
  const bf16* x = (const bf16*)d_in[0];
  const bf16* wqkv = (const bf16*)d_in[1];
  const bf16* wo = (const bf16*)d_in[2];
  const bf16* w1 = (const bf16*)d_in[4];
  const bf16* w2 = (const bf16*)d_in[5];
  bf16* out = (bf16*)d_out;

  void* fn = nullptr;
  cudaDriverEntryPointQueryResult qr;
  cudaGetDriverEntryPoint("cuTensorMapEncodeTiled", &fn, cudaEnableDefault, &qr);
  EncodeFn enc = (EncodeFn)fn;
  void *pOT, *pHc;
  cudaGetSymbolAddress(&pOT, g_OT);
  cudaGetSymbolAddress(&pHc, g_hc);
  CUtensorMap tmX, tmXt, tmWqkv, tmOT, tmWo, tmHc, tmW1, tmW2;
  make_map2(enc, &tmX, x, DM, SEQ, 64, 128, CU_TENSOR_MAP_SWIZZLE_128B);
  make_map2(enc, &tmWqkv, wqkv, NQKV, DM, 32, 64, CU_TENSOR_MAP_SWIZZLE_64B);
  make_map2(enc, &tmOT, pOT, SEQ, DM, 64, 64, CU_TENSOR_MAP_SWIZZLE_128B);
  make_map2(enc, &tmWo, wo, DM, DM, 32, 192, CU_TENSOR_MAP_SWIZZLE_64B);
  make_map2(enc, &tmXt, x, DM, SEQ, 144, 64, CU_TENSOR_MAP_SWIZZLE_NONE);
  make_map2(enc, &tmHc, pHc, DM, SEQ, 64, 64, CU_TENSOR_MAP_SWIZZLE_128B);
  {
    const cuuint64_t dims[3] = {64, DM, DFF / 64}, strides[2] = {DFF * 2, 128};
    const cuuint32_t box[3] = {64, 32, 3};
    make_map(enc, &tmW1, w1, 3, dims, strides, box, CU_TENSOR_MAP_SWIZZLE_128B);
  }
  make_map2(enc, &tmW2, w2, DM, DFF, 64, 96, CU_TENSOR_MAP_SWIZZLE_128B);

  cudaFuncSetAttribute(k_qkv, cudaFuncAttributeMaxDynamicSharedMemorySize, QKV_SMEM);
  cudaFuncSetAttribute(k_attn, cudaFuncAttributeMaxDynamicSharedMemorySize, ATT_SMEM);
  cudaFuncSetAttribute(k_ffn, cudaFuncAttributeMaxDynamicSharedMemorySize, FFN_SMEM);

  launch(k_qkv, 128, 384, QKV_SMEM, 2, false, tmX, tmWqkv, x, wqkv);
  launch(k_attn, 132, 512, ATT_SMEM, 1, true, tmOT, tmWo, tmXt, wo, w1, w2, 0u);
  launch(k_ffn, 128, 384, FFN_SMEM, 2, true, tmHc, tmW1, tmW2, out, 0u);
}
```
